```python
import torch

def _softmax(x, axis=-1):
    return torch.softmax(x, dim=axis)
def _gelu(x):
    return torch.nn.functional.gelu(x, approximate="tanh")
def _silu(x):
    return torch.nn.functional.silu(x)
def _sigmoid(x):
    return torch.sigmoid(x)
def _layernorm(x, axis=-1, eps=1e-5):
    m = x.mean(dim=axis, keepdim=True)
    v = x.var(dim=axis, keepdim=True, unbiased=False)
    return (x - m) / torch.sqrt(v + eps)
def _scatter_add(tgt, idx, src, axis=0):
    return tgt.clone().index_add_(axis, idx, src)
def _segment_sum(src, seg, n):
    out = torch.zeros((n,) + src.shape[1:], dtype=src.dtype)
    return out.index_add_(0, seg, src)
def _pad(x, pw):
    flat = tuple(v for pair in reversed(pw) for v in pair)
    return torch.nn.functional.pad(x, flat)

kernel_name = 'gated_mix__sliding_block_cached__dense_activation_squared_relu__decode'

def setup_inputs():

    _w = (lambda a: (lambda t: t.to(torch.bfloat16) if t.is_floating_point() else t)(torch.as_tensor(a)))
    def _A_setup():
        B, Sq, D = 2, 1, 576
        Hq, Hkv, Sk, Dh = 32, 16, 32768, 128
        assert Hq % Hkv == 0, (Hq, Hkv)
        return {
            "x": _w((lambda *s: torch.randn(*s, dtype=torch.bfloat16) * 0.05)(B, Sq, D)),
            "k_cache": _w((lambda *s: torch.randn(*s, dtype=torch.bfloat16) * 6.4)(B, Hkv, Sk, Dh)),
            "v_cache": _w((lambda *s: torch.randn(*s, dtype=torch.bfloat16) * 0.4)(B, Hkv, Sk, Dh)),
            "wq": _w((lambda *s: torch.randn(*s, dtype=torch.bfloat16) * 6.4)(D, Hq * Dh) * (D ** -0.5)),
            "wo": _w((lambda *s: torch.randn(*s, dtype=torch.bfloat16) * 0.4)(Hq * Dh, D) * ((Hq * Dh) ** -0.5)),
        }
    _A_in = _A_setup()

    def _B_setup():
        B, S, D, F = 2, 1, 576, 4608
        return {
            "x": _w((lambda *s: torch.randn(*s, dtype=torch.bfloat16) * 0.05)(B, S, D)),
            "w1": _w((lambda *s: torch.randn(*s, dtype=torch.bfloat16) * 0.05)(D, F)),
            "b1": _w((lambda *s: torch.randn(*s, dtype=torch.bfloat16) * 0.05)(F)),
            "w2": _w((lambda *s: torch.randn(*s, dtype=torch.bfloat16) * 0.05)(F, D)),
            "b2": _w((lambda *s: torch.randn(*s, dtype=torch.bfloat16) * 0.05)(D)),
        }
    _B_in = _B_setup()

    return {
        "A_x": _A_in["x"],
        "A_k_cache": _A_in["k_cache"],
        "A_v_cache": _A_in["v_cache"],
        "A_wq": _A_in["wq"],
        "A_wo": _A_in["wo"],
        "B_x": _B_in["x"],
        "B_w1": _B_in["w1"],
        "B_b1": _B_in["b1"],
        "B_w2": _B_in["w2"],
        "B_b2": _B_in["b2"],
        "gate_w": _w((lambda *s: torch.randn(*s, dtype=torch.bfloat16) * 0.05)(576) * 16.0),
    }

def reference(A_x, A_k_cache, A_v_cache, A_wq, A_wo, B_x, B_w1, B_b1, B_w2, B_b2, gate_w):
    def _A_ref(x, k_cache, v_cache, wq, wo):
        B, Sq, D = x.shape
        Hq, Dh = 32, 128
        Hkv, Sk = k_cache.shape[1], k_cache.shape[2]
        W = min(4096, max(256, Sk // 4))
        rep = Hq // Hkv
        q = (lambda x, *d: x.permute(*d))((x @ wq).reshape(B, Sq, Hq, Dh), 0, 2, 1, 3)
        k = (lambda x, n, axis: torch.repeat_interleave(x, n, dim=axis))(k_cache[:, :, Sk - W:, :], rep, axis=1)
        v = (lambda x, n, axis: torch.repeat_interleave(x, n, dim=axis))(v_cache[:, :, Sk - W:, :], rep, axis=1)
        scores = torch.einsum("bhqd,bhkd->bhqk", q, k) * (Dh ** -0.5)
        p = _softmax(scores, axis=-1)
        o = torch.einsum("bhqk,bhkd->bhqd", p, v)
        return (lambda x, *d: x.permute(*d))(o, 0, 2, 1, 3).reshape(B, Sq, Hq * Dh) @ wo

    def _B_ref(x, w1, b1, w2, b2):
        h = torch.einsum("bsd,df->bsf", x, w1) + b1
        zero = torch.zeros_like(h)
        r = torch.where(h > zero, h, zero)
        h = r * r
        out = torch.einsum("bsf,fd->bsd", h, w2) + b2
        return out

    x = A_x
    g = _sigmoid((x * gate_w).sum(-1, keepdims=True))
    a = _A_ref(x, A_k_cache, A_v_cache, A_wq, A_wo)
    b = _B_ref(x, B_w1, B_b1, B_w2, B_b2)
    return g * a + (1 - g) * b
```

```cpp
#include <cuda_runtime.h>
#include <cuda_bf16.h>
#include <stdint.h>

namespace {

constexpr int D_MODEL = 576;
constexpr int HKV = 16;
constexpr int SK = 32768;
constexpr int WIN = 4096;
constexpr int FF = 4608;
constexpr int QCOLS = 4096;

constexpr int NCTA = 128;
constexpr int NWARP = 14;
constexpr int NTHR = NWARP * 32;

#define TILE_KEYS 64
#define STAGES 8
#define WINDOW 4
#define WINDOW0 4
#define NWQ 9
#define NW1 81
#define WQW 2
#define W1W 2
#define W1_AFTER -1
#define EARLY 7
#define FSLEEP 0
constexpr int TILE_BYTES = TILE_KEYS * 256;
constexpr int NT = 1024 / TILE_KEYS;
constexpr int KPW = TILE_KEYS / 8;
constexpr int ROWB = D_MODEL * 2;

constexpr int W1_STRIDE = 576 + 16;
constexpr int PIECE = 4 * ROWB;
constexpr int PSTRIDE = PIECE + 16;

constexpr int SM_RING = 0;
constexpr int SM_WB = SM_RING + STAGES * TILE_BYTES;
constexpr int SM_WQ = SM_WB;
constexpr int SM_W1 = SM_WB + D_MODEL * 64;
constexpr int WB_BYTES = D_MODEL * 64 + 72 * W1_STRIDE;
constexpr int SM_WO = SM_WB;
constexpr int SM_W2 = SM_WB + 8 * PSTRIDE;
static_assert(17 * PSTRIDE <= WB_BYTES, "wb");
constexpr int SM_SC = SM_WB + WB_BYTES;
constexpr int SM_Q = SM_SC + 8 * 128 * 8;
constexpr int SM_QP = SM_Q + 256 * 4;
constexpr int SM_CB = SM_QP + 8 * 64 * 4;
constexpr int SM_ML = SM_CB + 4 * 80 * 2;
constexpr int SM_MISC = SM_ML + 8 * 16;
constexpr int SM_BAR = SM_MISC + 16;
constexpr int NBAR = 2 * STAGES + 12;
static_assert(NBAR <= 32, "bars");
constexpr int SM_TOTAL = SM_BAR + NBAR * 8;
static_assert(SM_TOTAL <= 227 * 1024, "smem");

constexpr unsigned SPIN_LIMIT = 1u << 22;

__device__ unsigned g_ep[NCTA][16];
__device__ unsigned long long g_qx[HKV][2][256];
__device__ ulonglong2 g_hx[HKV][8][288];
__device__ ulonglong2 g_ml[HKV][8][2];
__device__ unsigned long long g_ox[HKV][8][8][32];
__device__ ulonglong2 g_fx[288][NCTA][2];

#define TS(i) do { } while (0)

__device__ __forceinline__ uint32_t smem_u32(const void* p) { return (uint32_t)__cvta_generic_to_shared(p); }
__device__ __forceinline__ void mbar_init(uint32_t bar, int cnt) {
    asm volatile("mbarrier.init.shared::cta.b64 [%0], %1;" ::"r"(bar), "r"(cnt) : "memory");
}
__device__ __forceinline__ void mbar_expect_tx(uint32_t bar, uint32_t bytes) {
    asm volatile("mbarrier.arrive.expect_tx.shared::cta.b64 _, [%0], %1;" ::"r"(bar), "r"(bytes) : "memory");
}
__device__ __forceinline__ void mbar_arrive(uint32_t bar) {
    asm volatile("mbarrier.arrive.shared::cta.b64 _, [%0];" ::"r"(bar) : "memory");
}
__device__ __forceinline__ bool mbar_try(uint32_t bar, uint32_t parity) {
    uint32_t ok;
    asm volatile(
        "{\n.reg .pred p;\nmbarrier.try_wait.parity.shared::cta.b64 p, [%1], %2;\nselp.u32 %0, 1, 0, p;\n}\n"
        : "=r"(ok) : "r"(bar), "r"(parity) : "memory");
    return ok != 0;
}
__device__ __forceinline__ bool mbar_test(uint32_t bar, uint32_t parity) {
    uint32_t ok;
    asm volatile(
        "{\n.reg .pred p;\nmbarrier.test_wait.parity.shared::cta.b64 p, [%1], %2;\nselp.u32 %0, 1, 0, p;\n}\n"
        : "=r"(ok) : "r"(bar), "r"(parity) : "memory");
    return ok != 0;
}
__device__ __forceinline__ void mbar_wait(uint32_t bar, uint32_t parity) {
    unsigned n = 0;
    while (!mbar_try(bar, parity)) {
        if (++n > SPIN_LIMIT) __trap();
    }
}
__device__ __forceinline__ void bulk_load(uint32_t dst, const void* src, uint32_t bytes, uint32_t bar, uint64_t pol) {
    asm volatile(
        "cp.async.bulk.shared::cluster.global.mbarrier::complete_tx::bytes.L2::cache_hint [%0], [%1], %2, [%3], %4;"
        ::"r"(dst), "l"(src), "r"(bytes), "r"(bar), "l"(pol) : "memory");
}
__device__ __forceinline__ void cp16(uint32_t dst, const void* src) {
    asm volatile("cp.async.cg.shared.global [%0], [%1], 16;" ::"r"(dst), "l"(src) : "memory");
}
__device__ __forceinline__ void cp_commit() { asm volatile("cp.async.commit_group;" ::: "memory"); }
template <int N>
__device__ __forceinline__ void cp_wait() { asm volatile("cp.async.wait_group %0;" ::"n"(N) : "memory"); }
__device__ __forceinline__ float bf_lo(uint32_t u) { return __uint_as_float(u << 16); }
__device__ __forceinline__ float bf_hi(uint32_t u) { return __uint_as_float(u & 0xffff0000u); }
__device__ __forceinline__ float bf2f(__nv_bfloat16 v) { return __bfloat162float(v); }

__device__ __forceinline__ unsigned long long pack_tag(float v, unsigned tag) {
    return ((unsigned long long)tag << 32) | (unsigned long long)__float_as_uint(v);
}
__device__ __forceinline__ void st_tag(unsigned long long* p, unsigned long long v) {
    asm volatile("st.relaxed.gpu.global.b64 [%0], %1;" ::"l"(p), "l"(v) : "memory");
}
__device__ __forceinline__ void st_tag2(void* p, unsigned long long a, unsigned long long b) {
    asm volatile("st.relaxed.gpu.global.v2.b64 [%0], {%1, %2};" ::"l"(p), "l"(a), "l"(b) : "memory");
}
__device__ __forceinline__ unsigned long long ld_tag(const void* p) {
    unsigned long long v;
    asm volatile("ld.relaxed.gpu.global.b64 %0, [%1];" : "=l"(v) : "l"(p) : "memory");
    return v;
}
__device__ __forceinline__ ulonglong2 ld_tag2(const void* p) {
    ulonglong2 v;
    asm volatile("ld.relaxed.gpu.global.v2.b64 {%0, %1}, [%2];" : "=l"(v.x), "=l"(v.y) : "l"(p) : "memory");
    return v;
}
__device__ __forceinline__ unsigned tag_of(unsigned long long v) { return (unsigned)(v >> 32); }
__device__ __forceinline__ float val_of(unsigned long long v) { return __uint_as_float((unsigned)v); }
__device__ __forceinline__ void bar_sync(int id, int n) { asm volatile("bar.sync %0, %1;" ::"r"(id), "r"(n) : "memory"); }

__device__ __forceinline__ void ldsm4t(uint32_t (&a)[4], uint32_t addr) {
    asm volatile("ldmatrix.sync.aligned.m8n8.x4.trans.shared.b16 {%0,%1,%2,%3}, [%4];"
                 : "=r"(a[0]), "=r"(a[1]), "=r"(a[2]), "=r"(a[3]) : "r"(addr) : "memory");
}
__device__ __forceinline__ void ldsm2t(uint32_t (&a)[2], uint32_t addr) {
    asm volatile("ldmatrix.sync.aligned.m8n8.x2.trans.shared.b16 {%0,%1}, [%2];"
                 : "=r"(a[0]), "=r"(a[1]) : "r"(addr) : "memory");
}
__device__ __forceinline__ void mma16(float (&c)[4], const uint32_t (&a)[4], uint32_t b0, uint32_t b1) {
    asm volatile("mma.sync.aligned.m16n8k16.row.col.f32.bf16.bf16.f32 {%0,%1,%2,%3}, {%4,%5,%6,%7}, {%8,%9}, {%0,%1,%2,%3};"
                 : "+f"(c[0]), "+f"(c[1]), "+f"(c[2]), "+f"(c[3])
                 : "r"(a[0]), "r"(a[1]), "r"(a[2]), "r"(a[3]), "r"(b0), "r"(b1));
}
__device__ __forceinline__ void mma8(float (&c)[4], const uint32_t (&a)[2], uint32_t b0) {
    asm volatile("mma.sync.aligned.m16n8k8.row.col.f32.bf16.bf16.f32 {%0,%1,%2,%3}, {%4,%5}, {%6}, {%0,%1,%2,%3};"
                 : "+f"(c[0]), "+f"(c[1]), "+f"(c[2]), "+f"(c[3])
                 : "r"(a[0]), "r"(a[1]), "r"(b0));
}
template <int STRIDE>
__device__ __forceinline__ void gemv72(float (&c)[4], uint32_t addr, const uint32_t (&xb)[9]) {
    c[0] = c[1] = c[2] = c[3] = 0.f;
#pragma unroll
    for (int ks = 0; ks < 4; ks++) {
        uint32_t a[4];
        ldsm4t(a, addr + ks * 16 * STRIDE);
        mma16(c, a, xb[2 * ks], xb[2 * ks + 1]);
    }
    uint32_t a2[2];
    ldsm2t(a2, addr + 64 * STRIDE);
    mma8(c, a2, xb[8]);
}
__device__ __forceinline__ void put_coef(__nv_bfloat16* cb, int b, int k, float v) {
    const __nv_bfloat16 hi = __float2bfloat16(v);
    cb[b * 80 + k] = hi;
    cb[(2 + b) * 80 + k] = __float2bfloat16(v - bf2f(hi));
}

__global__ void __launch_bounds__(NTHR, 1)
fused_decode_kernel(const __nv_bfloat16* __restrict__ x, const __nv_bfloat16* __restrict__ kc,
                    const __nv_bfloat16* __restrict__ vc, const __nv_bfloat16* __restrict__ wq,
                    const __nv_bfloat16* __restrict__ wo, const __nv_bfloat16* __restrict__ w1,
                    const __nv_bfloat16* __restrict__ b1, const __nv_bfloat16* __restrict__ w2,
                    const __nv_bfloat16* __restrict__ b2, const __nv_bfloat16* __restrict__ gate_w,
                    __nv_bfloat16* __restrict__ out) {
    extern __shared__ __align__(128) unsigned char smem[];
    const int tid = threadIdx.x, warp = tid >> 5, lane = tid & 31;
    const int cta = blockIdx.x;
    const int hkv = cta >> 3, r = cta & 7, bb = r >> 2, sp = r & 3;
    const int g = lane >> 2, t4 = lane & 3;
    const uint32_t sbase = smem_u32(smem);
    const uint32_t bar_full = sbase + SM_BAR, bar_empty = bar_full + 8 * STAGES;
    const uint32_t bar_w2 = bar_empty + 8 * STAGES, bar_wo = bar_w2 + 16;
    const uint32_t bar_w1free = bar_w2 + 32, bar_gate = bar_w2 + 40, bar_h = bar_w2 + 48, bar_o = bar_w2 + 56;
    const uint32_t bar_wq = bar_w2 + 64, bar_ml = bar_w2 + 72, bar_v = bar_w2 + 80;
    const uint32_t bar_w1l = bar_w2 + 88;

    __nv_bfloat16* s_cb = reinterpret_cast<__nv_bfloat16*>(smem + SM_CB);
    float* s_q = reinterpret_cast<float*>(smem + SM_Q);
    float* s_qp = reinterpret_cast<float*>(smem + SM_QP);
    float2* s_m = reinterpret_cast<float2*>(smem + SM_ML);
    float2* s_l = s_m + 8;
    float* s_gate = reinterpret_cast<float*>(smem + SM_MISC);

    if (tid == 0) TS(0);

    if (warp == 8) {
        if (lane == 0) {
#pragma unroll
            for (int i = 0; i < NBAR; i++)
                mbar_init(bar_full + 8 * i, (i >= STAGES && i < 2 * STAGES) || (i >= 2 * STAGES + 8 && i < 2 * STAGES + 11) ? 8 : 1);
            asm volatile("fence.mbarrier_init.release.cluster;" ::: "memory");
        }
        uint64_t pol;
        asm volatile("createpolicy.fractional.L2::evict_first.b64 %0, 1.0;" : "=l"(pol));
        const size_t kvoff = ((size_t)(bb * HKV + hkv) * SK + (SK - WIN) + sp * 1024) * 256;
        if (lane == 0) TS(20);
        __syncthreads();
        if (lane == 0) TS(21);
        constexpr int NITEM = 2 * NT + 4;
        uint32_t watch = 0;
        int witem = 47;
        if (lane >= 24 && lane < 24 + WQW) watch = bar_wq;
        if (lane >= 26 && lane < 26 + W1W) watch = bar_w1l;
        int st = 0;
        uint32_t ph = 0;
#pragma unroll 1
        for (int i = 0; i < NITEM; i++) {
            const int win = i < STAGES ? WINDOW0 : WINDOW;
            if (i >= STAGES && i < 2 * NT) mbar_wait(bar_empty + 8 * st, ph ^ 1u);
            unsigned n = 0;
            while (true) {
                if (watch && mbar_test(watch & ~1u, watch & 1u)) {
                    watch = 0;
                }
                if (__popc(__ballot_sync(0xffffffffu, watch != 0)) < win) break;
                if (++n > SPIN_LIMIT) __trap();
            }
            if (i < 2 * NT) {
                if (lane == 0) {
                    const char* src = reinterpret_cast<const char*>(i < NT ? kc : vc) + kvoff +
                                      (size_t)(i & (NT - 1)) * TILE_BYTES;
                    mbar_expect_tx(bar_full + 8 * st, TILE_BYTES);
                    bulk_load(sbase + SM_RING + st * TILE_BYTES, src, TILE_BYTES, bar_full + 8 * st, pol);
                }
                if (lane == 0 && i < 2) TS(22 + i);
                if (lane == st) { watch = (bar_full + 8 * st) | ph; witem = i; }
                if (++st == STAGES) { st = 0; ph ^= 1u; }
            } else {
                const int w = i - 2 * NT;
                const uint32_t cur = bar_w2 + 8 * w;
                mbar_wait(bar_w1free, 0);
                const int np = (w == 1) ? 5 : 4;
                const int pc = (w & 1) * 4 + lane;
                const char* src = w < 2 ? reinterpret_cast<const char*>(w2) + (size_t)(hkv * 288 + r * 36) * ROWB
                                        : reinterpret_cast<const char*>(wo) + (size_t)(hkv * 256 + r * 32) * ROWB;
                if (lane == 0) mbar_expect_tx(cur, np * PIECE);
                __syncwarp();
                if (lane < np)
                    bulk_load(sbase + (w < 2 ? SM_W2 : SM_WO) + pc * PSTRIDE, src + pc * PIECE, PIECE, cur, pol);
                if (lane == 16 + w) { watch = cur; witem = i; }
            }
        }
        if (lane == 0) TS(13);
        return;
    }

    unsigned ep;
    asm volatile("ld.relaxed.gpu.global.u32 %0, [%1];" : "=r"(ep) : "l"(&g_ep[cta][warp]) : "memory");

    if (warp >= 10) {
        __syncthreads();
        const unsigned tag = ep + 1u;
        if (lane == 0) g_ep[cta][warp] = tag;
        if (warp == 10) {
            mbar_wait(bar_ml, 0);
            if (lane < 2) {
                float m = -INFINITY, l = 0.f;
#pragma unroll
                for (int w = 0; w < 8; w++) {
                    const float2 a = s_m[w], b = s_l[w];
                    m = fmaxf(m, lane ? a.y : a.x);
                    l += lane ? b.y : b.x;
                }
                st_tag2(&g_ml[hkv][r][lane], pack_tag(m, tag), pack_tag(l, tag));
            }
            float fac;
            {
                ulonglong2 ml;
                unsigned n = 0;
                while (true) {
                    ml = ld_tag2(&g_ml[hkv][lane & 7][r >> 2]);
                    if (__all_sync(0xffffffffu, tag_of(ml.x) == tag && tag_of(ml.y) == tag)) break;
                    __nanosleep(200);
                    if (++n > SPIN_LIMIT) __trap();
                }
                const float m = val_of(ml.x);
                float mm = fmaxf(m, __shfl_xor_sync(0xffffffffu, m, 1));
                mm = fmaxf(mm, __shfl_xor_sync(0xffffffffu, mm, 2));
                const float f = exp2f(m - mm);
                float l = f * val_of(ml.y);
                l += __shfl_xor_sync(0xffffffffu, l, 1);
                l += __shfl_xor_sync(0xffffffffu, l, 2);
                mbar_wait(bar_gate, 0);
                fac = f / l * s_gate[(lane >> 2) & 1];
            }
            float fs[8];
#pragma unroll
            for (int s = 0; s < 8; s++) fs[s] = __shfl_sync(0xffffffffu, fac, s);
        if (lane == 0) TS(16);
            float o0, o1;
            unsigned n = 0;
            if (!(EARLY & 2)) mbar_wait(bar_v, 0);
            while (true) {
                unsigned long long v[8];
#pragma unroll
                for (int s = 0; s < 8; s++) v[s] = ld_tag(&g_ox[hkv][r][s][lane]);
                bool ok = true;
                o0 = o1 = 0.f;
#pragma unroll
                for (int s = 0; s < 4; s++) {
                    ok = ok && tag_of(v[s]) == tag && tag_of(v[s + 4]) == tag;
                    o0 = fmaf(fs[s], val_of(v[s]), o0);
                    o1 = fmaf(fs[s + 4], val_of(v[s + 4]), o1);
                }
                if (__all_sync(0xffffffffu, ok)) break;
                if (n == 0) mbar_wait(bar_v, 0);
                if (++n > SPIN_LIMIT) __trap();
            }
            put_coef(s_cb, 0, t4 * 8 + g, o0);
            put_coef(s_cb, 1, t4 * 8 + g, o1);
            __syncwarp();
            if (lane == 0) mbar_arrive(bar_o);
            if (lane == 0) TS(9);
        } else if (cta < 96) {
            const int own = cta * 3 + warp - 11;
            const int b = own / 144, col = (own - b * 144) / 4 * 16 + (own & 3) * 2 + (lane & 1);
            float s0 = bf2f(b2[col]), s1 = bf2f(b2[col + 8]);
            mbar_wait(bar_gate, 0);
            const float gb = lane < 2 ? 1.f - s_gate[b] : 0.f;
            s0 *= gb;
            s1 *= gb;
            mbar_wait(EARLY & 4 ? bar_ml : bar_o, 0);
            const ulonglong2* base = &g_fx[own][0][0] + lane;
            unsigned pend = 0xffu, n = 0;
            while (true) {
                ulonglong2 v[8];
#pragma unroll
                for (int i = 0; i < 8; i++)
                    if (pend & (1u << i)) v[i] = ld_tag2(base + i * 32);
#pragma unroll
                for (int i = 0; i < 8; i++)
                    if ((pend & (1u << i)) && tag_of(v[i].x) == tag && tag_of(v[i].y) == tag) {
                        s0 += val_of(v[i].x);
                        s1 += val_of(v[i].y);
                        pend &= ~(1u << i);
                    }
                if (__all_sync(0xffffffffu, pend == 0)) break;
                if (n == 0) mbar_wait(bar_o, 0);
                if (FSLEEP) __nanosleep(FSLEEP);
                if (++n > SPIN_LIMIT) __trap();
            }
            if (warp == 11 && lane == 0) TS(11);
#pragma unroll
            for (int o = 2; o < 32; o <<= 1) {
                s0 += __shfl_xor_sync(0xffffffffu, s0, o);
                s1 += __shfl_xor_sync(0xffffffffu, s1, o);
            }
            if (lane < 2) {
                out[b * D_MODEL + col] = __float2bfloat16(s0);
                out[b * D_MODEL + col + 8] = __float2bfloat16(s1);
            }
            if (warp == 11 && lane == 0) TS(12);
        }
        return;
    }

    uint32_t xb[9];
    {
        const uint32_t* xp = reinterpret_cast<const uint32_t*>(x + (g & 1) * D_MODEL + 72 * (warp < 8 ? warp : r)) + t4;
#pragma unroll
        for (int i = 0; i < 9; i++) xb[i] = (g < 2) ? __ldg(xp + 4 * i) : 0u;
    }
    const int lrow = ((lane >> 4) << 3) + (lane & 7), lcol = ((lane >> 3) & 1) * 16;
    float facc[4][4];
    unsigned tag;

    if (warp == 9) {
        __syncthreads();
        {
            const char* p = reinterpret_cast<const char*>(w1) + ((size_t)(72 * r) * FF + hkv * 288) * 2;
#pragma unroll 3
            for (int i = 0; i < NW1; i++) {
                const int c = i * 32 + lane;
                const int row = c / 36, ch = c - row * 36;
                cp16(sbase + SM_W1 + row * W1_STRIDE + ch * 16, p + (size_t)row * (FF * 2) + ch * 16);
            }
            cp_commit();
        }
        float b1a = bf2f(b1[hkv * 288 + r * 36 + lane]);
        float b1b = bf2f(b1[hkv * 288 + r * 36 + 32 + (lane & 3)]);
        float d0 = 0.f, d1 = 0.f;
        {
            const uint32_t* x32 = reinterpret_cast<const uint32_t*>(x);
            const uint32_t* g32 = reinterpret_cast<const uint32_t*>(gate_w);
#pragma unroll
            for (int i = 0; i < 9; i++) {
                const uint32_t u0 = __ldg(x32 + lane + 32 * i), u1 = __ldg(x32 + 288 + lane + 32 * i);
                const uint32_t uw = __ldg(g32 + lane + 32 * i);
                d0 = fmaf(bf_lo(u0), bf_lo(uw), d0);
                d0 = fmaf(bf_hi(u0), bf_hi(uw), d0);
                d1 = fmaf(bf_lo(u1), bf_lo(uw), d1);
                d1 = fmaf(bf_hi(u1), bf_hi(uw), d1);
            }
        }
        tag = ep + 1u;
        if (lane == 0) g_ep[cta][warp] = tag;
        if (lane < 24) reinterpret_cast<uint32_t*>(s_cb)[(lane / 6) * 40 + 34 + lane % 6] = 0u;
#pragma unroll
        for (int o = 16; o > 0; o >>= 1) {
            d0 += __shfl_xor_sync(0xffffffffu, d0, o);
            d1 += __shfl_xor_sync(0xffffffffu, d1, o);
        }
        const float g0 = 1.f / (1.f + __expf(-d0)), g1 = 1.f / (1.f + __expf(-d1));
        if (lane == 0) {
            s_gate[0] = g0;
            s_gate[1] = g1;
            mbar_arrive(bar_gate);
        }
        cp_wait<0>();
        __syncwarp();
        if (lane == 0) mbar_arrive(bar_w1l);
#pragma unroll 2
        for (int mt = 0; mt < 18; mt++) {
            float c[4];
            gemv72<W1_STRIDE>(c, sbase + SM_W1 + lrow * W1_STRIDE + lcol + mt * 32, xb);
            if (t4 == 0) {
                st_tag2(&g_hx[hkv][r][mt * 16 + g], pack_tag(c[0], tag), pack_tag(c[1], tag));
                st_tag2(&g_hx[hkv][r][mt * 16 + 8 + g], pack_tag(c[2], tag), pack_tag(c[3], tag));
            }
        }
        asm volatile("fence.proxy.async.shared::cta;" ::: "memory");
        __syncwarp();
        if (lane == 0) mbar_arrive(bar_w1free);
        if (lane == 0) TS(14);
        mbar_wait(bar_ml, 0);
#pragma unroll 1
        for (int rnd = 0; rnd < 2; rnd++) {
            const int f = rnd ? 32 + (lane & 3) : lane;
            float h0, h1;
            unsigned n = 0;
            while (true) {
                ulonglong2 v[8];
#pragma unroll
                for (int s = 0; s < 8; s++) v[s] = ld_tag2(&g_hx[hkv][s][r * 36 + f]);
                bool ok = true;
                h0 = h1 = rnd ? b1b : b1a;
#pragma unroll
                for (int s = 0; s < 8; s++) {
                    ok = ok && tag_of(v[s].x) == tag && tag_of(v[s].y) == tag;
                    h0 += val_of(v[s].x);
                    h1 += val_of(v[s].y);
                }
                if (ok) break;
                __nanosleep(500);
                if (++n > SPIN_LIMIT) __trap();
            }
            h0 = fmaxf(h0, 0.f);
            h1 = fmaxf(h1, 0.f);
            const int kp = 32 + (rnd ? f : (f & 3) * 8 + (f >> 2));
            put_coef(s_cb, 0, kp, h0 * h0 * (1.f - g0));
            put_coef(s_cb, 1, kp, h1 * h1 * (1.f - g1));
        }
        __syncwarp();
        if (lane == 0) mbar_arrive(bar_h);
        if (lane == 0) TS(15);
    } else {
        {
            const char* p = reinterpret_cast<const char*>(wq) + ((size_t)(72 * warp + g) * QCOLS + hkv * 256 + r * 32) * 2 + t4 * 16;
            const uint32_t d = sbase + SM_WQ + (72 * warp + g) * 64 + ((t4 ^ (g >> 1)) << 4);
#pragma unroll
            for (int i = 0; i < NWQ; i++) cp16(d + i * 8 * 64, p + (size_t)i * 8 * QCOLS * 2);
            cp_commit();
        }
        unsigned long long qv = 0;
        if (EARLY & 1) qv = ld_tag(&g_qx[hkv][bb][tid]);
        __syncthreads();
        if (tid == 0) TS(1);
        cp_wait<0>();
        __syncwarp();
        if (lane == 0) mbar_arrive(bar_wq);
        if (tid == 0) TS(2);
#pragma unroll
        for (int mt = 0; mt < 2; mt++) {
            float c[4];
            const int ch = (mt * 2 + ((lane >> 3) & 1)) ^ ((lane >> 1) & 3);
            gemv72<64>(c, sbase + SM_WQ + (72 * warp + lrow) * 64 + ch * 16, xb);
            if (t4 == 0) {
                float* qp = s_qp + warp * 64 + mt * 16 + g;
                qp[0] = c[0];
                qp[32] = c[1];
                qp[8] = c[2];
                qp[40] = c[3];
            }
        }
        asm volatile("fence.proxy.async.shared::cta;" ::: "memory");
        tag = ep + 1u;
        bar_sync(1, 256);
        if (warp < 2) {
            float q = 0.f;
#pragma unroll
            for (int w = 0; w < 8; w++) q += s_qp[w * 64 + tid];
            st_tag(&g_qx[hkv][warp][r * 32 + lane], pack_tag(q * (0.08838834764831845f * 1.4426950408889634f), tag));
        }
        if (lane == 0) g_ep[cta][warp] = tag;
        if (tid == 0) TS(3);
        {
            unsigned n = 0;
            while (tag_of(qv) != tag) {
                qv = ld_tag(&g_qx[hkv][bb][tid]);
                if (++n > SPIN_LIMIT) __trap();
            }
            s_q[tid] = val_of(qv);
        }
        bar_sync(1, 256);
        if (tid == 0) TS(4);
        const int half = lane >> 4, chunk = lane & 15;
        float q0[8], q1[8];
        {
            const float4 a = *reinterpret_cast<const float4*>(s_q + chunk * 8);
            const float4 b = *reinterpret_cast<const float4*>(s_q + chunk * 8 + 4);
            const float4 c = *reinterpret_cast<const float4*>(s_q + 128 + chunk * 8);
            const float4 d = *reinterpret_cast<const float4*>(s_q + 128 + chunk * 8 + 4);
            q0[0] = a.x; q0[1] = a.y; q0[2] = a.z; q0[3] = a.w; q0[4] = b.x; q0[5] = b.y; q0[6] = b.z; q0[7] = b.w;
            q1[0] = c.x; q1[1] = c.y; q1[2] = c.z; q1[3] = c.w; q1[4] = d.x; q1[5] = d.y; q1[6] = d.z; q1[7] = d.w;
        }
        float* s_sc = reinterpret_cast<float*>(smem + SM_SC) + warp * 256;
        const bool b3 = lane & 8, b2b = lane & 4, b1b = lane & 2;
        float mx = -INFINITY;
        int st = 0;
        uint32_t ph = 0;
#pragma unroll 1
        for (int t = 0; t < NT; t++) {
            mbar_wait(bar_full + 8 * st, ph);
            const uint4* tp = reinterpret_cast<const uint4*>(smem + SM_RING + st * TILE_BYTES + warp * (KPW * 256)) + lane;
#pragma unroll 1
            for (int gk = 0; gk < KPW / 8; gk++) {
                uint4 kv[4];
#pragma unroll
                for (int i = 0; i < 4; i++) kv[i] = tp[gk * 128 + i * 32];
                float s[8];
#pragma unroll
                for (int i = 0; i < 4; i++) {
                    const uint32_t u[4] = {kv[i].x, kv[i].y, kv[i].z, kv[i].w};
                    float sa = 0.f, sb = 0.f;
#pragma unroll
                    for (int e = 0; e < 4; e++) {
                        const float lo = bf_lo(u[e]), hi = bf_hi(u[e]);
                        sa = fmaf(q0[2 * e], lo, sa);
                        sb = fmaf(q1[2 * e], lo, sb);
                        sa = fmaf(q0[2 * e + 1], hi, sa);
                        sb = fmaf(q1[2 * e + 1], hi, sb);
                    }
                    s[2 * i] = sa;
                    s[2 * i + 1] = sb;
                }
                float u4[4], u2[2], w;
#pragma unroll
                for (int j = 0; j < 4; j++) {
                    const float send = b3 ? s[j] : s[j + 4];
                    const float keep = b3 ? s[j + 4] : s[j];
                    u4[j] = keep + __shfl_xor_sync(0xffffffffu, send, 8);
                }
#pragma unroll
                for (int j = 0; j < 2; j++) {
                    const float send = b2b ? u4[j] : u4[j + 2];
                    const float keep = b2b ? u4[j + 2] : u4[j];
                    u2[j] = keep + __shfl_xor_sync(0xffffffffu, send, 4);
                }
                {
                    const float send = b1b ? u2[0] : u2[1];
                    const float keep = b1b ? u2[1] : u2[0];
                    w = keep + __shfl_xor_sync(0xffffffffu, send, 2);
                }
                w += __shfl_xor_sync(0xffffffffu, w, 1);
                mx = fmaxf(mx, w);
                const int j = (lane >> 1) & 7;
                const int key = t * KPW + gk * 8 + (j >> 1) * 2 + half;
                if ((lane & 1) == 0) s_sc[key * 2 + (j & 1)] = w;
            }
            __syncwarp();
            if (lane == 0) mbar_arrive(bar_empty + 8 * st);
            if (++st == STAGES) { st = 0; ph ^= 1; }
        }
        if (tid == 0) TS(5);
        mx = fmaxf(mx, __shfl_xor_sync(0xffffffffu, mx, 16));
        mx = fmaxf(mx, __shfl_xor_sync(0xffffffffu, mx, 8));
        mx = fmaxf(mx, __shfl_xor_sync(0xffffffffu, mx, 4));
        if ((lane & ~2) == 0) reinterpret_cast<float*>(s_m)[warp * 2 + (lane >> 1)] = mx;
        bar_sync(1, 256);
        float m0 = -INFINITY, m1 = -INFINITY;
#pragma unroll
        for (int w = 0; w < 8; w++) {
            const float2 e = s_m[w];
            m0 = fmaxf(m0, e.x);
            m1 = fmaxf(m1, e.y);
        }
        float l0 = 0.f, l1 = 0.f;
#pragma unroll
        for (int j = 0; j < 4; j++) {
            float2 sv = reinterpret_cast<float2*>(s_sc)[lane + 32 * j];
            sv.x = exp2f(sv.x - m0);
            sv.y = exp2f(sv.y - m1);
            l0 += sv.x;
            l1 += sv.y;
            reinterpret_cast<float2*>(s_sc)[lane + 32 * j] = sv;
        }
#pragma unroll
        for (int o = 16; o > 0; o >>= 1) {
            l0 += __shfl_xor_sync(0xffffffffu, l0, o);
            l1 += __shfl_xor_sync(0xffffffffu, l1, o);
        }
        if (lane == 0) {
            s_l[warp] = make_float2(l0, l1);
            mbar_arrive(bar_ml);
        }
        __syncwarp();
        float o0[8], o1[8];
#pragma unroll
        for (int e = 0; e < 8; e++) o0[e] = o1[e] = 0.f;
#pragma unroll 1
        for (int t = 0; t < NT; t++) {
            mbar_wait(bar_full + 8 * st, ph);
            const uint4* tp = reinterpret_cast<const uint4*>(smem + SM_RING + st * TILE_BYTES + warp * (KPW * 256)) + lane;
            const float2* pp = reinterpret_cast<const float2*>(s_sc) + t * KPW + half;
#pragma unroll 4
            for (int i = 0; i < KPW / 2; i++) {
                const uint4 vv = tp[i * 32];
                const float2 p = pp[2 * i];
                const uint32_t u[4] = {vv.x, vv.y, vv.z, vv.w};
#pragma unroll
                for (int e = 0; e < 4; e++) {
                    const float lo = bf_lo(u[e]), hi = bf_hi(u[e]);
                    o0[2 * e] = fmaf(p.x, lo, o0[2 * e]);
                    o0[2 * e + 1] = fmaf(p.x, hi, o0[2 * e + 1]);
                    o1[2 * e] = fmaf(p.y, lo, o1[2 * e]);
                    o1[2 * e + 1] = fmaf(p.y, hi, o1[2 * e + 1]);
                }
            }
            __syncwarp();
            if (lane == 0) mbar_arrive(bar_empty + 8 * st);
            if (++st == STAGES) { st = 0; ph ^= 1; }
        }
        if (lane == 0) mbar_arrive(bar_v);
        if (tid == 0) TS(6);
        {
            float k8[8];
#pragma unroll
            for (int e = 0; e < 8; e++) {
                const float send = half ? o0[e] : o1[e];
                const float keep = half ? o1[e] : o0[e];
                k8[e] = keep + __shfl_xor_sync(0xffffffffu, send, 16);
            }
            float4* pr = reinterpret_cast<float4*>(s_sc + half * 128 + chunk * 8);
            pr[0] = make_float4(k8[0], k8[1], k8[2], k8[3]);
            pr[1] = make_float4(k8[4], k8[5], k8[6], k8[7]);
        }
        bar_sync(1, 256);
        {
            const float* s_red = reinterpret_cast<const float*>(smem + SM_SC);
            float o = 0.f;
#pragma unroll
            for (int w = 0; w < 8; w++) o += s_red[w * 256 + tid];
            st_tag(&g_ox[hkv][warp][r][lane], pack_tag(o, tag));
        }
        if (tid == 0) TS(7);
        mbar_wait(bar_h, 0);
    }

    const int widx = warp < 8 ? warp : 8;
    const uint32_t fa = sbase + SM_WB + (lane & 7) * PSTRIDE + (lane >> 4) * ROWB + lcol + widx * 128;
    const uint32_t* cbp = reinterpret_cast<const uint32_t*>(s_cb) + (g & 3) * 40 + t4;
    {
        uint32_t cb[5];
#pragma unroll
        for (int i = 0; i < 5; i++) cb[i] = g < 4 ? cbp[16 + 4 * i] : 0u;
        mbar_wait(bar_w2, 0);
        mbar_wait(bar_w2 + 8, 0);
#pragma unroll
        for (int j = 0; j < 4; j++) {
            facc[j][0] = facc[j][1] = facc[j][2] = facc[j][3] = 0.f;
#pragma unroll
            for (int ks = 0; ks < 2; ks++) {
                uint32_t a[4];
                ldsm4t(a, fa + 8 * PSTRIDE + ks * 2 * ROWB + j * 32);
                mma16(facc[j], a, cb[2 * ks], cb[2 * ks + 1]);
            }
            uint32_t a2[2];
            ldsm2t(a2, sbase + SM_W2 + 8 * PSTRIDE + (lane & 3) * ROWB + lcol + widx * 128 + j * 32);
            mma8(facc[j], a2, cb[4]);
        }
    }
    if (tid == 0) TS(8);
    {
        mbar_wait(bar_wo, 0);
        mbar_wait(bar_wo + 8, 0);
        if (tid == 0) TS(17);
        uint32_t a[4][2][4];
#pragma unroll
        for (int j = 0; j < 4; j++)
#pragma unroll
            for (int ks = 0; ks < 2; ks++) ldsm4t(a[j][ks], fa + ks * 2 * ROWB + j * 32);
        mbar_wait(bar_o, 0);
        if (tid == 0) TS(18);
        uint32_t cb[4];
#pragma unroll
        for (int i = 0; i < 4; i++) cb[i] = g < 4 ? cbp[4 * i] : 0u;
#pragma unroll
        for (int ks = 0; ks < 2; ks++)
#pragma unroll
            for (int j = 0; j < 4; j++) mma16(facc[j], a[j][ks], cb[2 * ks], cb[2 * ks + 1]);
#pragma unroll
        for (int j = 0; j < 4; j++) {
            const float s0 = t4 ? facc[j][0] : facc[j][1], s1 = t4 ? facc[j][2] : facc[j][3];
            const float k0 = t4 ? facc[j][1] : facc[j][0], k1 = t4 ? facc[j][3] : facc[j][2];
            const float v0 = k0 + __shfl_xor_sync(0xffffffffu, s0, 1);
            const float v1 = k1 + __shfl_xor_sync(0xffffffffu, s1, 1);
            if (t4 < 2)
                st_tag2(&g_fx[(t4 * 36 + widx * 4 + j) * 4 + (g >> 1)][cta][g & 1], pack_tag(v0, tag), pack_tag(v1, tag));
        }
    }
    if (tid == 0) TS(10);
}

}

extern "C" void kernel_launch(void* const* d_in, const int* in_sizes, int n_in, void* d_out, int out_size) {
    (void)in_sizes; (void)n_in; (void)out_size;
    const __nv_bfloat16* x = (const __nv_bfloat16*)d_in[0];
    const __nv_bfloat16* kc = (const __nv_bfloat16*)d_in[1];
    const __nv_bfloat16* vc = (const __nv_bfloat16*)d_in[2];
    const __nv_bfloat16* wq = (const __nv_bfloat16*)d_in[3];
    const __nv_bfloat16* wo = (const __nv_bfloat16*)d_in[4];
    const __nv_bfloat16* w1 = (const __nv_bfloat16*)d_in[6];
    const __nv_bfloat16* b1 = (const __nv_bfloat16*)d_in[7];
    const __nv_bfloat16* w2 = (const __nv_bfloat16*)d_in[8];
    const __nv_bfloat16* b2 = (const __nv_bfloat16*)d_in[9];
    const __nv_bfloat16* gw = (const __nv_bfloat16*)d_in[10];
    cudaFuncSetAttribute(fused_decode_kernel, cudaFuncAttributeMaxDynamicSharedMemorySize, SM_TOTAL);
    fused_decode_kernel<<<NCTA, NTHR, SM_TOTAL, cudaStreamPerThread>>>(x, kc, vc, wq, wo, w1, b1, w2, b2, gw,
                                                                      (__nv_bfloat16*)d_out);
}
```

```cpp
#include <cuda.h>
#include <cuda_runtime.h>
#include <cuda_bf16.h>
#include <stdint.h>

namespace {

constexpr int D_MODEL = 576;
constexpr int HKV = 16;
constexpr int SK = 32768;
constexpr int WIN = 4096;
constexpr int FF = 4608;
constexpr int QCOLS = 4096;

constexpr int NCTA = 128;
constexpr int NWARP = 14;
constexpr int NTHR = NWARP * 32;

#define TILE_KEYS 64
#define STAGES 8
#define WINDOW 3
#define WMAX 8
#define PACE 665
#define PACE0 800
#define FIRST 1
#define WQW 2
#define W1POS 8
#define W2P 16
#define WOP 13
#define MLS 2500
#define VUN 2
#define WOPF 20
#define QS0 1200
#define FSTRIDE 256
constexpr int VUNR = VUN;
constexpr int TILE_BYTES = TILE_KEYS * 256;
constexpr int NT = 1024 / TILE_KEYS;
constexpr int ROWB = D_MODEL * 2;

constexpr int W1_STRIDE = 288;
constexpr int W1_BOX = 72 * W1_STRIDE;

constexpr int SM_RING = 0;
constexpr int SM_WB = SM_RING + STAGES * TILE_BYTES;
constexpr int SM_WQ = SM_WB;
constexpr int SM_W1 = SM_WB + D_MODEL * 64;
constexpr int W2S = ROWB + 16;
constexpr int WB_BYTES = 32 * ROWB + 128 + 36 * W2S + 64;
static_assert(D_MODEL * 64 + 2 * W1_BOX <= WB_BYTES && WB_BYTES % 128 == 0, "wb");
constexpr int SM_WO = SM_WB;
constexpr int SM_W2 = SM_WB + 32 * ROWB + 128;
constexpr int PT_HI = 528, PT_WARP = 1152;
constexpr int SM_P = SM_WB + WB_BYTES;
constexpr int SM_Z = SM_P + 8 * PT_WARP + 32;
constexpr int SM_Q = SM_Z + 512;
constexpr int SM_CB = SM_Q + 8 * 64 * 4;
constexpr int SM_MISC = SM_CB + 4 * 80 * 2;
constexpr int SM_ROW = SM_MISC + 32;
constexpr int SM_X = SM_ROW + 160;
constexpr int SM_BAR = SM_X + 2 * ROWB;
constexpr int NBAR = 2 * STAGES + 16;
constexpr int SM_TOTAL = SM_BAR + NBAR * 8;
static_assert(SM_TOTAL <= 227 * 1024, "smem");

constexpr unsigned SPIN_LIMIT = 1u << 22;

#define QL 33
#define ML 33
#define OL 33
#define OS (12 * OL)
#define OA(line, slot, e) sc->oa[((line) * OL + (slot) * OS) * 8 + (e)]
struct Scratch {
    unsigned ep[NCTA][16];
    uint32_t q[256 * QL * 32];
    float4 oa[(11 * OL + 31 * OS + 1) * 8];
    ulonglong2 hx[HKV][8][288];
    ulonglong2 ml[256 * ML * 8];
    float4 fa[48 * FSTRIDE];
};
__device__ __align__(256) Scratch g_scratch;

__device__ __forceinline__ uint32_t smem_u32(const void* p) { return (uint32_t)__cvta_generic_to_shared(p); }
__device__ __forceinline__ void mbar_init(uint32_t bar, int cnt) {
    asm volatile("mbarrier.init.shared::cta.b64 [%0], %1;" ::"r"(bar), "r"(cnt) : "memory");
}
__device__ __forceinline__ void mbar_expect_tx(uint32_t bar, uint32_t bytes) {
    asm volatile("mbarrier.arrive.expect_tx.shared::cta.b64 _, [%0], %1;" ::"r"(bar), "r"(bytes) : "memory");
}
__device__ __forceinline__ void mbar_arrive(uint32_t bar) {
    asm volatile("mbarrier.arrive.shared::cta.b64 _, [%0];" ::"r"(bar) : "memory");
}
__device__ __forceinline__ bool mbar_try(uint32_t bar, uint32_t parity) {
    uint32_t ok;
    asm volatile(
        "{\n.reg .pred p;\nmbarrier.try_wait.parity.shared::cta.b64 p, [%1], %2;\nselp.u32 %0, 1, 0, p;\n}\n"
        : "=r"(ok) : "r"(bar), "r"(parity) : "memory");
    return ok != 0;
}
__device__ __forceinline__ bool mbar_test(uint32_t bar, uint32_t parity) {
    uint32_t ok;
    asm volatile(
        "{\n.reg .pred p;\nmbarrier.test_wait.parity.shared::cta.b64 p, [%1], %2;\nselp.u32 %0, 1, 0, p;\n}\n"
        : "=r"(ok) : "r"(bar), "r"(parity) : "memory");
    return ok != 0;
}
__device__ __forceinline__ void mbar_wait(uint32_t bar, uint32_t parity) {
    unsigned n = 0;
    while (!mbar_try(bar, parity)) {
        if (++n > SPIN_LIMIT) __trap();
    }
}
__device__ __forceinline__ void bulk_load(uint32_t dst, const void* src, uint32_t bytes, uint32_t bar, uint64_t pol) {
    asm volatile(
        "cp.async.bulk.shared::cluster.global.mbarrier::complete_tx::bytes.L2::cache_hint [%0], [%1], %2, [%3], %4;"
        ::"r"(dst), "l"(src), "r"(bytes), "r"(bar), "l"(pol) : "memory");
}
__device__ __forceinline__ void tensor_load(uint32_t dst, const CUtensorMap* map, int c0, int c1, uint32_t bar, uint64_t pol) {
    asm volatile(
        "cp.async.bulk.tensor.2d.shared::cluster.global.mbarrier::complete_tx::bytes.L2::cache_hint [%0], [%1, {%2, %3}], [%4], %5;"
        ::"r"(dst), "l"(map), "r"(c0), "r"(c1), "r"(bar), "l"(pol) : "memory");
}
__device__ __forceinline__ void tensor_load3(uint32_t dst, const CUtensorMap* map, int c1, int c2, uint32_t bar, uint64_t pol) {
    asm volatile(
        "cp.async.bulk.tensor.3d.shared::cluster.global.mbarrier::complete_tx::bytes.L2::cache_hint [%0], [%1, {%2, %3, %4}], [%5], %6;"
        ::"r"(dst), "l"(map), "r"(0), "r"(c1), "r"(c2), "r"(bar), "l"(pol) : "memory");
}
__device__ __forceinline__ void cp16(uint32_t dst, const void* src) {
    asm volatile("cp.async.cg.shared.global.L2::256B [%0], [%1], 16;" ::"r"(dst), "l"(src) : "memory");
}
__device__ __forceinline__ void cp_commit() { asm volatile("cp.async.commit_group;" ::: "memory"); }
template <int N>
__device__ __forceinline__ void cp_wait() { asm volatile("cp.async.wait_group %0;" ::"n"(N) : "memory"); }
__device__ __forceinline__ float bf_lo(uint32_t u) { return __uint_as_float(u << 16); }
__device__ __forceinline__ float bf_hi(uint32_t u) { return __uint_as_float(u & 0xffff0000u); }
__device__ __forceinline__ float bf2f(__nv_bfloat16 v) { return __bfloat162float(v); }

__device__ __forceinline__ unsigned long long pack_tag(float v, unsigned tag) {
    return ((unsigned long long)tag << 32) | (unsigned long long)__float_as_uint(v);
}
__device__ __forceinline__ void st_tag2(void* p, unsigned long long a, unsigned long long b) {
    asm volatile("st.relaxed.gpu.global.v2.b64 [%0], {%1, %2};" ::"l"(p), "l"(a), "l"(b) : "memory");
}
__device__ __forceinline__ unsigned long long ld_tag(const void* p) {
    unsigned long long v;
    asm volatile("ld.relaxed.gpu.global.b64 %0, [%1];" : "=l"(v) : "l"(p) : "memory");
    return v;
}
__device__ __forceinline__ ulonglong2 ld_tag2(const void* p) {
    ulonglong2 v;
    asm volatile("ld.relaxed.gpu.global.v2.b64 {%0, %1}, [%2];" : "=l"(v.x), "=l"(v.y) : "l"(p) : "memory");
    return v;
}
__device__ __forceinline__ float ld_f32(const void* p) {
    float v;
    asm volatile("ld.relaxed.gpu.global.f32 %0, [%1];" : "=f"(v) : "l"(p) : "memory");
    return v;
}
__device__ __forceinline__ uint32_t ld_u32(const void* p) {
    uint32_t v;
    asm volatile("ld.global.u32 %0, [%1];" : "=r"(v) : "l"(p) : "memory");
    return v;
}
__device__ __forceinline__ float count_base(unsigned tag) { return (float)((tag & 0x3fffu) << 8); }
__device__ __forceinline__ void wait_init(float c, const void* p, float base) {
    unsigned n = 0;
    while (!(c >= base && c < base + 256.f)) {
        c = ld_f32(p);
        if (++n > SPIN_LIMIT) __trap();
    }
}
__device__ __forceinline__ unsigned tag_of(unsigned long long v) { return (unsigned)(v >> 32); }
__device__ __forceinline__ float val_of(unsigned long long v) { return __uint_as_float((unsigned)v); }
__device__ __forceinline__ void bar_sync(int id, int n) { asm volatile("bar.sync %0, %1;" ::"r"(id), "r"(n) : "memory"); }

__device__ __forceinline__ void st_u32(void* p, uint32_t v) {
    asm volatile("st.relaxed.gpu.global.u32 [%0], %1;" ::"l"(p), "r"(v) : "memory");
}
__device__ __forceinline__ void red4(float4* p, float a, float b, float c) {
    asm volatile("red.relaxed.gpu.global.add.v4.f32 [%0], {%1, %2, %3, %4};" ::"l"(p), "f"(a), "f"(b), "f"(c), "f"(1.0f) : "memory");
}
__device__ __forceinline__ void lds128(uint32_t (&a)[4], uint32_t addr) {
    asm volatile("ld.shared.v4.u32 {%0,%1,%2,%3}, [%4];" : "=r"(a[0]), "=r"(a[1]), "=r"(a[2]), "=r"(a[3]) : "r"(addr) : "memory");
}
__device__ __forceinline__ void lds64(uint32_t& a, uint32_t& b, uint32_t addr) {
    asm volatile("ld.shared.v2.u32 {%0,%1}, [%2];" : "=r"(a), "=r"(b) : "r"(addr) : "memory");
}
__device__ __forceinline__ void delay_ns(uint32_t ns) {
    uint32_t t0, t, n = 0;
    asm volatile("mov.u32 %0, %globaltimer_lo;" : "=r"(t0));
    do {
        __nanosleep(100);
        asm volatile("mov.u32 %0, %globaltimer_lo;" : "=r"(t));
    } while (t - t0 < ns && ++n < 1000u);
}
__device__ __forceinline__ void ldsm4t(uint32_t (&a)[4], uint32_t addr) {
    asm volatile("ldmatrix.sync.aligned.m8n8.x4.trans.shared.b16 {%0,%1,%2,%3}, [%4];"
                 : "=r"(a[0]), "=r"(a[1]), "=r"(a[2]), "=r"(a[3]) : "r"(addr) : "memory");
}
__device__ __forceinline__ void ldsm2t(uint32_t (&a)[2], uint32_t addr) {
    asm volatile("ldmatrix.sync.aligned.m8n8.x2.trans.shared.b16 {%0,%1}, [%2];"
                 : "=r"(a[0]), "=r"(a[1]) : "r"(addr) : "memory");
}
__device__ __forceinline__ void mma16(float (&c)[4], const uint32_t (&a)[4], uint32_t b0, uint32_t b1) {
    asm volatile("mma.sync.aligned.m16n8k16.row.col.f32.bf16.bf16.f32 {%0,%1,%2,%3}, {%4,%5,%6,%7}, {%8,%9}, {%0,%1,%2,%3};"
                 : "+f"(c[0]), "+f"(c[1]), "+f"(c[2]), "+f"(c[3])
                 : "r"(a[0]), "r"(a[1]), "r"(a[2]), "r"(a[3]), "r"(b0), "r"(b1));
}
__device__ __forceinline__ void mma8(float (&c)[4], const uint32_t (&a)[2], uint32_t b0) {
    asm volatile("mma.sync.aligned.m16n8k8.row.col.f32.bf16.bf16.f32 {%0,%1,%2,%3}, {%4,%5}, {%6}, {%0,%1,%2,%3};"
                 : "+f"(c[0]), "+f"(c[1]), "+f"(c[2]), "+f"(c[3])
                 : "r"(a[0]), "r"(a[1]), "r"(b0));
}
template <int STRIDE>
__device__ __forceinline__ void gemv72(float (&c)[4], uint32_t addr, const uint32_t (&xb)[9]) {
    c[0] = c[1] = c[2] = c[3] = 0.f;
#pragma unroll
    for (int ks = 0; ks < 4; ks++) {
        uint32_t a[4];
        ldsm4t(a, addr + ks * 16 * STRIDE);
        mma16(c, a, xb[2 * ks], xb[2 * ks + 1]);
    }
    uint32_t a2[2];
    ldsm2t(a2, addr + 64 * STRIDE);
    mma8(c, a2, xb[8]);
}
__device__ __forceinline__ void put_coef(__nv_bfloat16* cb, int b, int k, float v) {
    const __nv_bfloat16 hi = __float2bfloat16(v);
    cb[2 * b * 80 + k] = hi;
    cb[(2 * b + 1) * 80 + k] = __float2bfloat16(v - bf2f(hi));
}

__global__ void __launch_bounds__(NTHR, 1)
fused_decode_kernel(const __nv_bfloat16* __restrict__ kc, const __nv_bfloat16* __restrict__ vc,
                    const __nv_bfloat16* __restrict__ wq, Scratch* __restrict__ sc,
                    const __nv_bfloat16* __restrict__ w2,
                    __nv_bfloat16* __restrict__ out,
                    const __nv_bfloat16* __restrict__ x, const __nv_bfloat16* __restrict__ b1,
                    const __nv_bfloat16* __restrict__ b2, const __nv_bfloat16* __restrict__ gate_w,
                    const __grid_constant__ CUtensorMap map_w1, const __grid_constant__ CUtensorMap map_wo) {
    extern __shared__ __align__(1024) unsigned char smem[];
    asm volatile(
        "{\n.reg .u32 t, c, o;\n.reg .u64 a;\n.reg .pred p;\nmov.u32 t, %%tid.x;\nmov.u32 c, %%ctaid.x;\n"
        "setp.lt.u32 p, t, 256;\nmul.lo.u32 o, c, 0x204000;\nshl.b32 t, t, 6;\nlop3.b32 o, o, 0x080fc000, t, 0xea;\n"
        "mad.wide.u32 a, o, 1, %0;\n@p prefetch.global.L2 [a + %1];\n}\n"
        ::"l"(kc), "n"((SK - WIN) * 256) : "memory");
    const int tid = threadIdx.x, warp = tid >> 5, lane = tid & 31;
    const int cta = blockIdx.x;
    const int hkv = cta >> 3, r = cta & 7, bb = cta >> 6, sp = cta & 63;
    const int g = lane >> 2, t4 = lane & 3;
    const uint32_t sbase = smem_u32(smem);
    const uint32_t bar_full = sbase + SM_BAR, bar_empty = bar_full + 8 * STAGES;
    const uint32_t bar_ml = bar_empty + 8 * STAGES, bar_wq = bar_ml + 8, bar_v = bar_ml + 16;
    const uint32_t bar_w2 = bar_ml + 24, bar_wo = bar_w2 + 16, bar_w1 = bar_w2 + 40;
    const uint32_t bar_gate = bar_w2 + 56, bar_h = bar_w2 + 64, bar_o = bar_w2 + 72;
    const uint32_t bar_x = bar_w2 + 80, bar_go = bar_w2 + 88;

    __nv_bfloat16* s_cb = reinterpret_cast<__nv_bfloat16*>(smem + SM_CB);
    float* s_q = reinterpret_cast<float*>(smem + SM_Q);
    float* s_gate = reinterpret_cast<float*>(smem + SM_MISC);
    volatile uint32_t* s_mask = reinterpret_cast<volatile uint32_t*>(s_gate + 4);

    volatile uint32_t* s_row = reinterpret_cast<volatile uint32_t*>(smem + SM_ROW);

    uint64_t pol;
    asm volatile("createpolicy.fractional.L2::evict_first.b64 %0, 1.0;" : "=l"(pol));
    const size_t kvoff = ((size_t)(bb * HKV) * SK + (SK - WIN) + sp * TILE_KEYS) * 256;
    constexpr size_t TSTRIDE = (size_t)SK * 256;
    if (tid == 256) {
#pragma unroll
        for (int i = 0; i < FIRST; i++) mbar_init(bar_full + 8 * i, 1);
        asm volatile("fence.mbarrier_init.release.cluster;" ::: "memory");
#pragma unroll
        for (int i = 0; i < FIRST; i++) {
            mbar_expect_tx(bar_full + 8 * i, TILE_BYTES);
            bulk_load(sbase + SM_RING + i * TILE_BYTES, reinterpret_cast<const char*>(kc) + kvoff + i * TSTRIDE,
                      TILE_BYTES, bar_full + 8 * i, pol);
        }
    }
    if (warp == 8) {
        uint32_t due;
        asm volatile("mov.u32 %0, %globaltimer_lo;" : "=r"(due));
        due += PACE0 + (36 + 16 * (FIRST - 3)) * PACE / 16;
        if (lane == 0) {
#pragma unroll
            for (int i = FIRST; i < NBAR; i++) mbar_init(bar_full + 8 * i, (i == 2 * STAGES || i == 2 * STAGES + 1) ? 8 : 1);
            asm volatile("fence.mbarrier_init.release.cluster;" ::: "memory");
        }
        __syncwarp();
        asm volatile("bar.arrive 0, %0;" ::"n"(NTHR) : "memory");
        constexpr int NITEM = 2 * NT + 7;
        uint32_t watch = 0;
        if (lane >= 24 && lane < 24 + WQW) watch = bar_wq;
        if (lane < FIRST) watch = bar_full + 8 * lane;
        int st = FIRST, tile = FIRST;
        uint32_t ph = 0;
#pragma unroll 1
        for (int i = FIRST; i < NITEM; i++) {
            const bool is_w1 = i >= W1POS && i < W1POS + 2;
            const bool is_tile = !is_w1 && tile < 2 * NT;
            unsigned n = 0;
            while (true) {
                if (watch && mbar_test(watch & ~1u, watch & 1u)) watch = 0;
                if (is_tile && tile >= STAGES && !mbar_test(bar_empty + 8 * st, ph ^ 1u)) {
                    if (++n > SPIN_LIMIT) __trap();
                    continue;
                }
                const int fl = __popc(__ballot_sync(0xffffffffu, watch != 0));
                if (fl < WINDOW) break;
                if (fl < WMAX) {
                    uint32_t now;
                    asm volatile("mov.u32 %0, %globaltimer_lo;" : "=r"(now));
                    if ((int)(now - due) >= 0) break;
                }
                if (++n > SPIN_LIMIT) __trap();
            }
            due += is_tile ? PACE : PACE * 20 / 16;
            if (i == WOPF && lane == 0) asm volatile("prefetch.tensormap [%0];" ::"l"(&map_wo) : "memory");
            if (is_tile) {
                if (lane == 0) {
                    const char* src = reinterpret_cast<const char*>(tile < NT ? kc : vc) + kvoff + (tile & (NT - 1)) * TSTRIDE;
                    mbar_expect_tx(bar_full + 8 * st, TILE_BYTES);
                    bulk_load(sbase + SM_RING + st * TILE_BYTES, src, TILE_BYTES, bar_full + 8 * st, pol);
                }
                if (lane == st) watch = (bar_full + 8 * st) | ph;
                tile++;
                if (++st == STAGES) { st = 0; ph ^= 1u; }
            } else if (is_w1) {
                const int w = i - W1POS;
                if (lane == 0) {
                    mbar_expect_tx(bar_w1 + 8 * w, W1_BOX);
                    tensor_load(sbase + SM_W1 + w * W1_BOX, &map_w1, hkv * 288 + w * 144, r * 72, bar_w1 + 8 * w, pol);
                }
                if (lane == 22 + w) watch = bar_w1 + 8 * w;
            } else {
                const int w = i - 2 * NT - 2;
                const int th = (cta + w) % 3;
                const uint32_t cur = bar_w2 + 8 * (w < 2 ? w : 2 + th);
                if (w < 2) {
                    if (lane == 0) mbar_arrive(bar_go + 8 * w);
                    due += (uint32_t)(PACE * W2P / 16 - PACE * 20 / 16);
                } else {
                    if (lane == 0) {
                        mbar_expect_tx(cur, 32 * 384);
                        tensor_load3(sbase + SM_WO + th * (32 * 384), &map_wo, 3 * th, cta * 32, cur, pol);
                    }
                    due += (uint32_t)(PACE * WOP / 16 - PACE * 20 / 16);
                }
                if (lane == 16 + w) watch = cur;
            }
        }
        return;
    }

    unsigned ep;
    asm volatile("ld.relaxed.gpu.global.u32 %0, [%1];" : "=r"(ep) : "l"(&sc->ep[cta][warp]) : "memory");
    unsigned tag;
    float fchk = -1.f;
    const int widx = warp < 8 ? warp : (warp == 9 ? 8 : warp - 2);
    float4* const facc_p = &sc->fa[(widx * 4 + (lane >> 3)) * FSTRIDE + (lane & 7)];
    const int lrow = ((lane >> 4) << 3) + (lane & 7), lcol = ((lane >> 3) & 1) * 16;

    if (warp >= 10) {
        if (warp == 11) reinterpret_cast<uint4*>(smem + SM_Z)[lane] = make_uint4(0u, 0u, 0u, 0u);
        bar_sync(0, NTHR);
        tag = ep + 1u;
        if (lane == 0) sc->ep[cta][warp] = tag;
        if (warp == 10) {
            const float base = count_base(tag);
            if (cta < 12) {
                const int col = cta * 48 + (t4 >> 1) * 8 + g;
                const float v0 = bf2f(b2[col]), v1 = bf2f(b2[col + 16]), v2 = bf2f(b2[col + 32]);
                mbar_wait(bar_gate, 0);
                const float gb = 1.f - s_gate[t4 & 1];
                st_tag2(&sc->fa[(cta * 4 + (lane >> 3)) * FSTRIDE + (lane & 7)],
                        pack_tag(v0 * gb, __float_as_uint(v1 * gb)), pack_tag(v2 * gb, __float_as_uint(base)));
            }
            const bool z = lane & 8;
            const float4* ap = &OA(z ? 8 + (r & 3) : r, (lane & 16) + hkv, lane & 7);
            ulonglong2 oa;
            unsigned n = 0;
            mbar_wait(bar_v, 0);
            while (true) {
                oa = ld_tag2(ap);
                if (__all_sync(0xffffffffu, tag_of(oa.y) == __float_as_uint(base + 64.f))) break;
                if (++n > SPIN_LIMIT) __trap();
            }
            const int k = (lane & 7) * 4;
            const float o1 = __uint_as_float(tag_of(oa.x));
            put_coef(s_cb, lane >> 4, z ? k + 3 : k, z && r >= 4 ? o1 : val_of(oa.x));
            if (!z) {
                put_coef(s_cb, lane >> 4, k + 1, o1);
                put_coef(s_cb, lane >> 4, k + 2, val_of(oa.y));
            }
            __syncwarp();
            if (lane == 0) mbar_arrive(bar_o);
            return;
        }
        mbar_wait(bar_h, 0);
    } else {
    uint32_t xb[9];
    const uint32_t* s_x = reinterpret_cast<const uint32_t*>(smem + SM_X);
    if (warp == 9) {
        uint32_t xv[18];
#pragma unroll
        for (int i = 0; i < 18; i++) xv[i] = ld_u32(reinterpret_cast<const uint32_t*>(x) + lane + 32 * i);
        bar_sync(0, NTHR);
        float b1a = bf2f(b1[hkv * 288 + r * 36 + lane]);
        float b1b = bf2f(b1[hkv * 288 + r * 36 + 32 + (lane & 3)]);
        float d0 = 0.f, d1 = 0.f;
        {
            const uint32_t* g32 = reinterpret_cast<const uint32_t*>(gate_w);
            uint32_t gw[9];
#pragma unroll
            for (int i = 0; i < 9; i++) gw[i] = ld_u32(g32 + lane + 32 * i);
#pragma unroll
            for (int i = 0; i < 18; i++) reinterpret_cast<uint32_t*>(smem + SM_X)[lane + 32 * i] = xv[i];
            __syncwarp();
            if (lane == 0) mbar_arrive(bar_x);
#pragma unroll
            for (int i = 0; i < 9; i++) xb[i] = s_x[(g & 1) * 288 + 36 * r + t4 + 4 * i];
#pragma unroll
            for (int i = 0; i < 9; i++) {
                const uint32_t u0 = s_x[lane + 32 * i], u1 = s_x[288 + lane + 32 * i], uw = gw[i];
                d0 = fmaf(bf_lo(u0), bf_lo(uw), d0);
                d0 = fmaf(bf_hi(u0), bf_hi(uw), d0);
                d1 = fmaf(bf_lo(u1), bf_lo(uw), d1);
                d1 = fmaf(bf_hi(u1), bf_hi(uw), d1);
            }
        }
        tag = ep + 1u;
        if (lane == 0) sc->ep[cta][warp] = tag;
#pragma unroll
        for (int i = 0; i < 3; i++) reinterpret_cast<uint32_t*>(s_cb)[(lane >> 3) * 40 + 16 + (lane & 7) * 3 + i] = 0u;
#pragma unroll
        for (int o = 16; o > 0; o >>= 1) {
            d0 += __shfl_xor_sync(0xffffffffu, d0, o);
            d1 += __shfl_xor_sync(0xffffffffu, d1, o);
        }
        const float g0 = 1.f / (1.f + __expf(-d0)), g1 = 1.f / (1.f + __expf(-d1));
        if (lane == 0) {
            s_gate[0] = g0;
            s_gate[1] = g1;
            mbar_arrive(bar_gate);
        }
#pragma unroll 1
        for (int bx = 0; bx < 2; bx++) {
            mbar_wait(bar_w1 + 8 * bx, 0);
#pragma unroll 3
            for (int mt = 0; mt < 9; mt++) {
                float c[4];
                gemv72<W1_STRIDE>(c, sbase + SM_W1 + bx * W1_BOX + lrow * W1_STRIDE + lcol + mt * 32, xb);
                if (t4 == 0) {
                    ulonglong2* hp = &sc->hx[hkv][r][bx * 144 + mt * 16 + g];
                    st_tag2(hp, pack_tag(c[0], tag), pack_tag(c[1], tag));
                    st_tag2(hp + 8, pack_tag(c[2], tag), pack_tag(c[3], tag));
                }
            }
        }
        asm volatile("fence.proxy.async.shared::cta;" ::: "memory");
        mbar_wait(bar_ml, 0);
        {
            float h0, h1, e0, e1;
            unsigned n = 0;
            while (true) {
                ulonglong2 v[9];
#pragma unroll
                for (int s = 0; s < 8; s++) v[s] = ld_tag2(&sc->hx[hkv][s][r * 36 + lane]);
                v[8] = ld_tag2(&sc->hx[hkv][g][r * 36 + 32 + t4]);
                bool ok = tag_of(v[8].x) == tag && tag_of(v[8].y) == tag;
                h0 = h1 = b1a;
#pragma unroll
                for (int s = 0; s < 8; s++) {
                    ok = ok && tag_of(v[s].x) == tag && tag_of(v[s].y) == tag;
                    h0 += val_of(v[s].x);
                    h1 += val_of(v[s].y);
                }
                e0 = val_of(v[8].x);
                e1 = val_of(v[8].y);
                if (__all_sync(0xffffffffu, ok)) break;
                __nanosleep(500);
                if (++n > SPIN_LIMIT) __trap();
            }
#pragma unroll
            for (int o = 4; o < 32; o <<= 1) {
                e0 += __shfl_xor_sync(0xffffffffu, e0, o);
                e1 += __shfl_xor_sync(0xffffffffu, e1, o);
            }
            h0 = fmaxf(h0, 0.f);
            h1 = fmaxf(h1, 0.f);
            e0 = fmaxf(e0 + b1b, 0.f);
            e1 = fmaxf(e1 + b1b, 0.f);
            const bool a0 = h0 > 0.f || h1 > 0.f, a1 = lane < 4 && (e0 > 0.f || e1 > 0.f);
            const uint32_t m0 = __ballot_sync(0xffffffffu, a0), m1 = __ballot_sync(0xffffffffu, a1);
            const uint32_t lt = (1u << lane) - 1u;
            if (a0) {
                const int kp = 32 + __popc(m0 & lt);
                s_row[kp - 32] = lane * ROWB;
                put_coef(s_cb, 0, kp, h0 * h0 * (1.f - g0));
                put_coef(s_cb, 1, kp, h1 * h1 * (1.f - g1));
            }
            if (a1) {
                const int kp = 32 + __popc(m0) + __popc(m1 & lt);
                s_row[kp - 32] = (lane + 32) * ROWB;
                put_coef(s_cb, 0, kp, e0 * e0 * (1.f - g0));
                put_coef(s_cb, 1, kp, e1 * e1 * (1.f - g1));
            }
            if (lane == 0) {
                s_mask[0] = m0;
                s_mask[1] = m1;
            }
        }
        __syncwarp();
        if (lane == 0) mbar_arrive(bar_h);
    } else {
        {
            const char* p = reinterpret_cast<const char*>(wq) + ((size_t)(72 * warp + g) * QCOLS + hkv * 256 + r * 32) * 2 + t4 * 16;
            const uint32_t d = sbase + SM_WQ + (72 * warp + g) * 64 + ((t4 ^ (g >> 1)) << 4);
#pragma unroll
            for (int i = 0; i < 9; i++) cp16(d + i * 8 * 64, p + (size_t)i * 8 * QCOLS * 2);
            cp_commit();
        }
        bar_sync(0, NTHR);
        mbar_wait(bar_x, 0);
#pragma unroll
        for (int i = 0; i < 9; i++) xb[i] = s_x[((g >> 1) & 1) * 288 + 36 * warp + t4 + 4 * i];
        cp_wait<0>();
        __syncwarp();
        if (lane == 0) mbar_arrive(bar_wq);
        tag = ep + 1u;
        const unsigned par = tag & 1u;
#pragma unroll
        for (int mt = 0; mt < 2; mt++) {
            float c[4];
            const int ch = (mt * 2 + ((lane >> 3) & 1)) ^ ((lane >> 1) & 3);
            gemv72<64>(c, sbase + SM_WQ + (72 * warp + lrow) * 64 + ch * 16, xb);
            s_q[warp * 64 + mt * 32 + (t4 & 1) * 16 + (t4 & 2) * 4 + g] = (t4 & 2) ? c[2] : c[0];
        }
        if (warp == 0) {
            bar_sync(1, 256);
            const int col = (lane & 6) * 4 + (lane & 1) * 4 + ((lane & 8) >> 2);
            const float2* pq = reinterpret_cast<const float2*>(s_q + (col & 16) * 2 + (lane & 16) + (col & 15));
            float qx = 0.f, qy = 0.f;
#pragma unroll
            for (int w = 0; w < 8; w++) {
                const float2 e = pq[w * 32];
                qx += e.x;
                qy += e.y;
            }
            uint32_t u;
            asm("cvt.rn.bf16x2.f32 %0, %1, %2;" : "=r"(u) : "f"(qy), "f"(qx));
            if (u == 0u) u = 0x8000u;
            uint32_t* qp = &sc->q[((lane >> 4) * 64 + (cta >> 1)) * (QL * 32) + (r & 1) * 16 + (lane & 15)];
            st_u32(qp + par * (128 * QL * 32), u);
            st_u32(qp + (par ^ 1u) * (128 * QL * 32), 0u);
        } else {
            asm volatile("bar.arrive 1, 256;" ::: "memory");
        }
        asm volatile("fence.proxy.async.shared::cta;" ::: "memory");
        if (lane == 0) sc->ep[cta][warp] = tag;
        if (sp < 24 && lane < 8)
            st_tag2(&OA(sp % 12, bb * 16 + warp + (sp / 12) * 8, lane), 0ull, pack_tag(0.f, __float_as_uint(count_base(tag))));
        float ichk = 0.f;
        if (sp < 24 && lane < 8) ichk = ld_f32(&OA(sp % 12, bb * 16 + warp + (sp / 12) * 8, lane).w);
        const uint32_t tile = sbase + SM_RING + warp * TILE_BYTES;
        const uint32_t bfull = bar_full + 8 * warp, bempty = bar_empty + 8 * warp;
        unsigned long long mla, mlb;
        float sa[4], s[4];
        delay_ns(QS0);
#pragma unroll 1
        for (int it = 0; it < 2; it++) {
            unsigned long long qb[4];
            {
                const unsigned long long* qp = reinterpret_cast<const unsigned long long*>(sc->q) +
                                               (((par * 2 + bb) * 16 + warp + 8 * it) * 4 + (g & 2)) * (QL * 16) + (g & 1) * 4 + t4;
                const int x = (g >> 2) * 8;
                unsigned n = 0;
                while (true) {
                    bool ok = true;
#pragma unroll
                    for (int i = 0; i < 4; i++) qb[i] = ld_tag(qp + (((i & 1) * 8) ^ x) + (i >> 1) * (QL * 16));
#pragma unroll
                    for (int i = 0; i < 4; i++) ok = ok && (unsigned)qb[i] != 0u && tag_of(qb[i]) != 0u;
                    if (__all_sync(0xffffffffu, ok)) break;
                    if (++n > SPIN_LIMIT) __trap();
                }
            }
            mbar_wait(bfull, it);
            const uint32_t ka = tile + g * 256 + (g & 1) * 64 + t4 * 16;
            float mx = -INFINITY;
#pragma unroll
            for (int u = 0; u < 4; u++) {
                float c[2][4];
#pragma unroll
                for (int y = 0; y < 2; y++) {
                    c[y][0] = c[y][1] = c[y][2] = c[y][3] = 0.f;
#pragma unroll
                    for (int i = 0; i < 4; i++) {
                        uint32_t a[4];
                        lds128(a, (ka ^ (((i ^ y) & 1) * 64)) + (i & 2) * 64 + (2 * u + y) * 2048);
                        mma16(c[y], a, (uint32_t)qb[i], tag_of(qb[i]));
                    }
                }
                sa[u] = s[u];
                s[u] = (((lane >> 1) ^ g) & 1 ? c[1][0] + c[1][3] : c[0][0] + c[0][3]) * (0.08838834764831845f * 1.4426950408889634f);
                mx = fmaxf(mx, s[u]);
            }
            __syncwarp();
            if (lane == 0) mbar_arrive(bempty);
#pragma unroll
            for (int o = 2; o < 32; o <<= 1) mx = fmaxf(mx, __shfl_xor_sync(0xffffffffu, mx, o));
            float l = (exp2f(s[0] - mx) + exp2f(s[1] - mx)) + (exp2f(s[2] - mx) + exp2f(s[3] - mx));
#pragma unroll
            for (int o = 2; o < 32; o <<= 1) l += __shfl_xor_sync(0xffffffffu, l, o);
            mla = mlb;
            mlb = pack_tag(mx, (__float_as_uint(l) & 0x7fffffffu) | (par << 31));
        }
        if (sp < 24 && lane < 8) wait_init(ichk, &OA(sp % 12, bb * 16 + warp + (sp / 12) * 8, lane).w, count_base(tag));
        __syncwarp();
        if (lane < 2) st_tag2(&sc->ml[((bb * 8 + warp) * 16 + (sp >> 2)) * (ML * 8) + (sp & 3) * 2 + lane], mla, mlb);
        if (lane == 0) mbar_arrive(bar_ml);
        fchk = ld_f32(&facc_p->w);
        mbar_wait(bar_gate, 0);
        const float gate = s_gate[bb];
        uint32_t* pt = reinterpret_cast<uint32_t*>(smem + SM_P + warp * PT_WARP) +
                       (((lane >> 1) ^ g) & 1) * 16 + (g >> 1) * 4 + (t4 & 1) * 2 + (g & 1);
        const uint32_t pb = (g >> 1) == t4 ? sbase + SM_P + warp * PT_WARP + (g & 1) * PT_HI : sbase + SM_Z;
        uint32_t pr[4];
        {
            ulonglong2 ml[4];
            unsigned n = 0;
            delay_ns(MLS);
            while (true) {
                bool ok = true;
#pragma unroll
                for (int i = 0; i < 4; i++) ml[i] = ld_tag2(&sc->ml[((bb * 8 + warp) * 16 + 4 * i + (lane >> 3)) * (ML * 8) + (lane & 7)]);
#pragma unroll
                for (int i = 0; i < 4; i++) ok = ok && (tag_of(ml[i].x) >> 31) == par && (tag_of(ml[i].y) >> 31) == par;
                if (__all_sync(0xffffffffu, ok)) break;
                __nanosleep(200);
                if (++n > SPIN_LIMIT) __trap();
            }
            float ma = fmaxf(fmaxf(val_of(ml[0].x), val_of(ml[1].x)), fmaxf(val_of(ml[2].x), val_of(ml[3].x)));
            float mb = fmaxf(fmaxf(val_of(ml[0].y), val_of(ml[1].y)), fmaxf(val_of(ml[2].y), val_of(ml[3].y)));
#pragma unroll
            for (int o = 2; o < 32; o <<= 1) {
                ma = fmaxf(ma, __shfl_xor_sync(0xffffffffu, ma, o));
                mb = fmaxf(mb, __shfl_xor_sync(0xffffffffu, mb, o));
            }
            float la = 0.f, lb = 0.f;
#pragma unroll
            for (int i = 0; i < 4; i++) {
                la = fmaf(exp2f(val_of(ml[i].x) - ma), fabsf(__uint_as_float(tag_of(ml[i].x))), la);
                lb = fmaf(exp2f(val_of(ml[i].y) - mb), fabsf(__uint_as_float(tag_of(ml[i].y))), lb);
            }
#pragma unroll
            for (int o = 2; o < 32; o <<= 1) {
                la += __shfl_xor_sync(0xffffffffu, la, o);
                lb += __shfl_xor_sync(0xffffffffu, lb, o);
            }
            const float fa = __fdividef(gate, la), fb = __fdividef(gate, lb);
#pragma unroll
            for (int u = 0; u < 4; u++)
                asm("cvt.rn.bf16x2.f32 %0, %1, %2;" : "=r"(pr[u]) : "f"(exp2f(s[u] - mb) * fb), "f"(exp2f(sa[u] - ma) * fa));
        }
#pragma unroll 1
        for (int it = 0; it < 2; it++) {
#pragma unroll
            for (int u = 0; u < 4; u++) {
                pt[u * 32] = pr[u] & 0xffffu;
                pt[u * 32 + PT_HI / 4] = pr[u] << 16;
                pr[u] >>= 16;
            }
            __syncwarp();
            float4* ap = &OA(lane >> 3, bb * 16 + warp + 8 * it, lane & 7);
            float c[4][2][4];
#pragma unroll
            for (int j = 0; j < 8; j++) c[j >> 1][j & 1][0] = c[j >> 1][j & 1][1] = c[j >> 1][j & 1][2] = c[j >> 1][j & 1][3] = 0.f;
            mbar_wait(bfull, it);
#pragma unroll VUNR
            for (int j = 0; j < 32; j += 4) {
#pragma unroll
                for (int i = 0; i < 4; i++) {
                    uint32_t a[4], p[4];
                    lds64(a[0], a[1], tile + lane * 8 + (j + i) * 512);
                    lds64(a[2], a[3], tile + lane * 8 + (j + i) * 512 + 256);
                    lds128(p, pb + (j + i) * 16);
                    mma16(c[i][0], a, p[0], p[1]);
                    mma16(c[i][1], a, p[2], p[3]);
                }
            }
            __syncwarp();
            if (lane == 0) mbar_arrive(bempty);
            float o[2][4];
#pragma unroll
            for (int j = 0; j < 8; j++) o[j >> 2][j & 3] = (c[0][j >> 2][j & 3] + c[1][j >> 2][j & 3]) + (c[2][j >> 2][j & 3] + c[3][j >> 2][j & 3]);
            {
            red4(ap, o[0][0], o[0][1], o[0][2]);
            red4(ap + 4 * 8 * OL, o[1][0], o[1][1], o[1][2]);
            red4(ap + 8 * 8 * OL, o[0][3], o[1][3], 0.f);
            }
            if (lane == 0 && warp + 8 * it == hkv) mbar_arrive(bar_v);
        }
        mbar_wait(bar_h, 0);
    }
    }

    if (warp == NWARP - 1) {
        const int n = __popc(s_mask[0]) + __popc(s_mask[1]), n0 = (n + 1) >> 1;
        const char* src = reinterpret_cast<const char*>(w2) + (size_t)(hkv * 288 + r * 36) * ROWB;
#pragma unroll
        for (int w = 0; w < 2; w++) {
            const int slot = (w ? n0 : 0) + lane, hi = w ? n : n0;
            const uint32_t ro = s_row[min(slot, 35)];
            const int cnt = __popc(__ballot_sync(0xffffffffu, slot < hi));
            mbar_wait(bar_go + 8 * w, 0);
            if (lane == 0) mbar_expect_tx(bar_w2 + 8 * w, cnt * ROWB);
            __syncwarp();
            if (slot < hi) bulk_load(sbase + SM_W2 + slot * W2S, src + ro, ROWB, bar_w2 + 8 * w, pol);
        }
    }
    const float base = count_base(tag);
    wait_init(fchk, &facc_p->w, base);
    const uint32_t* cbp = reinterpret_cast<const uint32_t*>(s_cb) + (g & 3) * 40 + t4;
    float facc[3][4];
    {
        uint32_t cb[5];
#pragma unroll
        for (int i = 0; i < 5; i++) cb[i] = cbp[16 + 4 * i];
        const int last = __popc(s_mask[0]) + __popc(s_mask[1]) - 1;
        const uint32_t wa = sbase + SM_W2 + lcol + widx * 96;
        const uint32_t r0 = wa + min(lrow, last) * W2S, r1 = wa + min(lrow + 16, last) * W2S;
        const uint32_t r2 = wa + min((lane & 7) + 32, last) * W2S;
#pragma unroll
        for (int j = 0; j < 3; j++) facc[j][0] = facc[j][1] = facc[j][2] = facc[j][3] = 0.f;
        mbar_wait(bar_w2, 0);
        mbar_wait(bar_w2 + 8, 0);
        if (last >= 0) {
#pragma unroll
            for (int j = 0; j < 3; j++) {
                uint32_t a[4], a2[2];
                ldsm4t(a, r0 + j * 32);
                mma16(facc[j], a, cb[0], cb[1]);
                ldsm4t(a, r1 + j * 32);
                mma16(facc[j], a, cb[2], cb[3]);
                ldsm2t(a2, r2 + j * 32);
                mma8(facc[j], a2, cb[4]);
            }
        }
    }
    __nv_bfloat16* op = out + (t4 & 1) * D_MODEL + widx * 48 + (t4 >> 1) * 8 + g;
    float4* fp = facc_p;
    float lastc = base + (float)(NCTA - 1);
    asm volatile("" : "+l"(op), "+l"(fp), "+f"(lastc));
    {
        uint32_t cb[4], a[6][4], ad[3];
#pragma unroll
        for (int j = 0; j < 3; j++) {
            const int off = (widx & 3) * 96 + j * 32 + lcol, line = lrow * 3 + (off >> 7);
            ad[j] = sbase + SM_WO + (widx >> 2) * (32 * 384) + line * 128 + ((((off >> 4) ^ line) & 7) << 4);
            ad[j] = __shfl_sync(0xffffffffu, ad[j], lane);
        }
        mbar_wait(bar_o, 0);
#pragma unroll
        for (int i = 0; i < 4; i++) cb[i] = cbp[4 * i];
        mbar_wait(bar_wo + 8 * (widx >> 2), 0);
#pragma unroll
        for (int j = 0; j < 3; j++) {
            ldsm4t(a[j], ad[j]);
            ldsm4t(a[j + 3], ad[j] + 16 * 384);
        }
#pragma unroll
        for (int j = 0; j < 3; j++) mma16(facc[j], a[j], cb[0], cb[1]);
#pragma unroll
        for (int j = 0; j < 3; j++) mma16(facc[j], a[j + 3], cb[2], cb[3]);
    }
    float v[3], old[4];
#pragma unroll
    for (int j = 0; j < 3; j++) v[j] = (t4 & 2) ? facc[j][2] + facc[j][3] : facc[j][0] + facc[j][1];
    asm volatile("atom.relaxed.gpu.global.add.v4.f32 {%0, %1, %2, %3}, [%4], {%5, %6, %7, %8};"
                 : "=f"(old[0]), "=f"(old[1]), "=f"(old[2]), "=f"(old[3])
                 : "l"(fp), "f"(v[0]), "f"(v[1]), "f"(v[2]), "f"(1.0f) : "memory");
    asm volatile(
        "{\n.reg .pred p;\n.reg .b16 a, b, c;\nsetp.eq.f32 p, %0, %1;\n"
        "cvt.rn.bf16.f32 a, %3;\ncvt.rn.bf16.f32 b, %4;\ncvt.rn.bf16.f32 c, %5;\n"
        "@p st.global.b16 [%2], a;\n@p st.global.b16 [%2+32], b;\n@p st.global.b16 [%2+64], c;\n}\n"
        ::"f"(old[3]), "f"(lastc), "l"(op), "f"(old[0] + v[0]), "f"(old[1] + v[1]), "f"(old[2] + v[2]) : "memory");
}

typedef CUresult (*EncodeFn)(CUtensorMap*, CUtensorMapDataType, cuuint32_t, void*, const cuuint64_t*, const cuuint64_t*,
                             const cuuint32_t*, const cuuint32_t*, CUtensorMapInterleave, CUtensorMapSwizzle,
                             CUtensorMapL2promotion, CUtensorMapFloatOOBfill);

void make_map(EncodeFn enc, CUtensorMap* m, const void* p, int cols, int rows, int bc, int br, CUtensorMapSwizzle sw) {
    const cuuint64_t dims[2] = {(cuuint64_t)cols, (cuuint64_t)rows};
    const cuuint64_t strides[1] = {(cuuint64_t)cols * 2};
    const cuuint32_t box[2] = {(cuuint32_t)bc, (cuuint32_t)br};
    const cuuint32_t es[2] = {1, 1};
    enc(m, CU_TENSOR_MAP_DATA_TYPE_BFLOAT16, 2, const_cast<void*>(p), dims, strides, box, es,
        CU_TENSOR_MAP_INTERLEAVE_NONE, sw, CU_TENSOR_MAP_L2_PROMOTION_NONE, CU_TENSOR_MAP_FLOAT_OOB_FILL_NONE);
}

}

extern "C" void kernel_launch(void* const* d_in, const int* in_sizes, int n_in, void* d_out, int out_size) {
    (void)in_sizes; (void)n_in; (void)out_size;
    const __nv_bfloat16* x = (const __nv_bfloat16*)d_in[0];
    const __nv_bfloat16* kc = (const __nv_bfloat16*)d_in[1];
    const __nv_bfloat16* vc = (const __nv_bfloat16*)d_in[2];
    const __nv_bfloat16* wq = (const __nv_bfloat16*)d_in[3];
    const __nv_bfloat16* wo = (const __nv_bfloat16*)d_in[4];
    const __nv_bfloat16* w1 = (const __nv_bfloat16*)d_in[6];
    const __nv_bfloat16* b1 = (const __nv_bfloat16*)d_in[7];
    const __nv_bfloat16* w2 = (const __nv_bfloat16*)d_in[8];
    const __nv_bfloat16* b2 = (const __nv_bfloat16*)d_in[9];
    const __nv_bfloat16* gw = (const __nv_bfloat16*)d_in[10];
    void* sc = nullptr;
    cudaGetSymbolAddress(&sc, g_scratch);
    void* fn = nullptr;
    cudaDriverEntryPointQueryResult qr;
    cudaGetDriverEntryPoint("cuTensorMapEncodeTiled", &fn, cudaEnableDefault, &qr);
    CUtensorMap m1, mo;
    make_map((EncodeFn)fn, &m1, w1, FF, D_MODEL, 144, 72, CU_TENSOR_MAP_SWIZZLE_NONE);
    {
        const cuuint64_t dims[3] = {64, 9, (cuuint64_t)QCOLS};
        const cuuint64_t strides[2] = {128, (cuuint64_t)ROWB};
        const cuuint32_t box[3] = {64, 3, 32};
        const cuuint32_t es[3] = {1, 1, 1};
        ((EncodeFn)fn)(&mo, CU_TENSOR_MAP_DATA_TYPE_BFLOAT16, 3, const_cast<__nv_bfloat16*>(wo), dims, strides, box, es,
            CU_TENSOR_MAP_INTERLEAVE_NONE, CU_TENSOR_MAP_SWIZZLE_128B, CU_TENSOR_MAP_L2_PROMOTION_NONE, CU_TENSOR_MAP_FLOAT_OOB_FILL_NONE);
    }
    cudaFuncSetAttribute(fused_decode_kernel, cudaFuncAttributeMaxDynamicSharedMemorySize, SM_TOTAL);
    fused_decode_kernel<<<NCTA, NTHR, SM_TOTAL, cudaStreamPerThread>>>(kc, vc, wq, (Scratch*)sc, w2, (__nv_bfloat16*)d_out, x, b1, b2,
                                                                      gw, m1, mo);
}
```
